```python
import torch

def _softmax(x, axis=-1):
    return torch.softmax(x, dim=axis)

def _gelu(x):
    return torch.nn.functional.gelu(x, approximate='tanh')

def _silu(x):
    return torch.nn.functional.silu(x)

def _sigmoid(x):
    return torch.sigmoid(x)

def _layernorm(x, axis=-1, eps=1e-05):
    m = x.mean(dim=axis, keepdim=True)
    v = x.var(dim=axis, keepdim=True, unbiased=False)
    return (x - m) / torch.sqrt(v + eps)

def _scatter_add(tgt, idx, src, axis=0):
    return tgt.clone().index_add_(axis, idx, src)

def _segment_sum(src, seg, n):
    out = torch.zeros((n,) + src.shape[1:], dtype=src.dtype)
    return out.index_add_(0, seg, src)

def _pad(x, pw):
    flat = tuple((v for pair in reversed(pw) for v in pair))
    return torch.nn.functional.pad(x, flat)
kernel_name = 'adaLN_cond__mha_block_cached__geglu_ffn__decode'

def setup_inputs():

    _w = lambda a: (lambda t: t.to(torch.bfloat16) if t.is_floating_point() else t)(torch.as_tensor(a))

    def _A_setup():
        B, Sq, D = (1, 1, 512)
        H, Sk, Dh = (32, 65536, 128)
        return {'x': _w((lambda *s: torch.randn(*s, dtype=torch.bfloat16) * 0.1)(B, Sq, D)), 'k_cache': _w((lambda *s: torch.randn(*s, dtype=torch.bfloat16) * 0.8)(B, H, Sk, Dh)), 'v_cache': _w((lambda *s: torch.randn(*s, dtype=torch.bfloat16) * 1.6)(B, H, Sk, Dh)), 'wq': _w((lambda *s: torch.randn(*s, dtype=torch.bfloat16) * 0.8)(D, H * Dh) * D ** (-0.5)), 'wo': _w((lambda *s: torch.randn(*s, dtype=torch.bfloat16) * 1.6)(H * Dh, D) * (H * Dh) ** (-0.5))}
    _A_in = _A_setup()

    def _B_setup():
        B, S, D, F = (1, 1, 512, 1792)
        return {'x': _w((lambda *s: torch.randn(*s, dtype=torch.bfloat16) * 0.1)(B, S, D)), 'w_gate': _w((lambda *s: torch.randn(*s, dtype=torch.bfloat16) * 0.4)(D, F)), 'w_up': _w((lambda *s: torch.randn(*s, dtype=torch.bfloat16) * 0.4)(D, F)), 'w_down': _w((lambda *s: torch.randn(*s, dtype=torch.bfloat16) * 0.4)(F, D))}
    _B_in = _B_setup()
    return {'A_x': _A_in['x'], 'A_k_cache': _A_in['k_cache'], 'A_v_cache': _A_in['v_cache'], 'A_wq': _A_in['wq'], 'A_wo': _A_in['wo'], 'B_x': _B_in['x'], 'B_w_gate': _B_in['w_gate'], 'B_w_up': _B_in['w_up'], 'B_w_down': _B_in['w_down'], 'c': _w((lambda *s: torch.randn(*s, dtype=torch.bfloat16) * 0.4)(1, 512) * 8.0), 'w_mod': _w((lambda *s: torch.randn(*s, dtype=torch.bfloat16) * 0.4)(512, 6 * 512) * 512 ** (-0.5) * 8.0)}

def reference(A_x, A_k_cache, A_v_cache, A_wq, A_wo, B_x, B_w_gate, B_w_up, B_w_down, c, w_mod):

    def _A_ref(x, k_cache, v_cache, wq, wo):
        B, Sq, D = x.shape
        H, Dh = (32, 128)
        q = (lambda x, *d: x.permute(*d))((x @ wq).reshape(B, Sq, H, Dh), 0, 2, 1, 3)
        scores = torch.einsum('bhqd,bhkd->bhqk', q, k_cache) * Dh ** (-0.5)
        p = _softmax(scores, axis=-1)
        o = torch.einsum('bhqk,bhkd->bhqd', p, v_cache)
        return (lambda x, *d: x.permute(*d))(o, 0, 2, 1, 3).reshape(B, Sq, H * Dh) @ wo

    def _B_ref(x, w_gate, w_up, w_down):
        return _gelu(x @ w_gate) * (x @ w_up) @ w_down
    x = A_x
    mod = (_silu(c) @ w_mod).reshape(c.shape[0], 6, 1, -1)
    sa, ca, ga, sb, cb, gb = (mod[:, 0].clone(), mod[:, 1].clone(), mod[:, 2].clone(), mod[:, 3].clone(), mod[:, 4].clone(), mod[:, 5].clone())
    h = _layernorm(x, axis=-1) * (1 + ca) + sa
    x = x + ga * _A_ref(h, A_k_cache, A_v_cache, A_wq, A_wo)
    h = _layernorm(x, axis=-1) * (1 + cb) + sb
    x = x + gb * _B_ref(h, B_w_gate, B_w_up, B_w_down)
    return x
```

```cpp
#include <cuda_runtime.h>
#include <cuda.h>
#include <cuda_bf16.h>
#include <stdint.h>

namespace {

constexpr int DM = 512;
constexpr int NH = 32;
constexpr int DH = 128;
constexpr int SK = 65536;
constexpr int FF = 1792;
constexpr int UNIT_KEYS = 64;
constexpr int UNITS_PER_HEAD = SK / UNIT_KEYS;
constexpr int NU = NH * UNITS_PER_HEAD;
constexpr int TILE_BYTES = UNIT_KEYS * DH * 2;
constexpr int NSLOT = 6;
#define WIN_TILES_V 3
constexpr int WIN_TILES = WIN_TILES_V;
#define WIN_PRE_V 3
constexpr int WIN_PRE = WIN_PRE_V;
#define TICKET_EARLY_V 0
constexpr bool TICKET_EARLY = TICKET_EARLY_V;
#define DRY_RUN_V 1
constexpr bool DRY_RUN = DRY_RUN_V;
#define PRO_ORDER_V 5
constexpr int PRO_ORDER = PRO_ORDER_V;
constexpr bool PRO_K1 = PRO_ORDER == 3 || PRO_ORDER == 4;
#define HALF_UNITS_V 0
constexpr int HALF_UNITS = HALF_UNITS_V;
constexpr unsigned NU1 = NU - HALF_UNITS;
constexpr unsigned NT = NU1 + 2 * HALF_UNITS;
#define FFN_KEEP_V 1
constexpr int FFN_KEEP = FFN_KEEP_V;
constexpr int MAXG = 144;
constexpr int NSLICE = 128;
constexpr int NFFN = 112;
constexpr int RED0 = 112;
constexpr int NRED = 8;
constexpr int NYP = NRED / 2;
#define PRE_MODE 0
#define PRE_VOTE(x) __any_sync(0xffffffffu, (x))
#define PRE_SPIN 300
#define FIN_GATE 2
#define FIN_DELAY_V 900
constexpr unsigned FIN_DELAY = FIN_DELAY_V;
#define FIN_GO(at) if (FIN_GATE == (at) && tid == 255 && live) asm volatile("st.volatile.shared.u32 [%0], %1;" ::"r"(sbase + SM_META + 60), "r"(1) : "memory");
constexpr int NFIN = 128;
constexpr int NTHREADS = 288;

constexpr float LOG2E = 1.4426950408889634f;
constexpr float QK_SCALE = 0.08838834764831845f;

__device__ uint2 g_mp[4][2 * DM];
__device__ uint2 g_mod[6 * DM];
__device__ uint2 g_qp[NH][4][DH];
__device__ __align__(128) uint32_t g_po[NH][MAXG][DH];
__device__ __align__(128) uint32_t g_pml[NH][MAXG][32];
__device__ __align__(128) uint32_t g_y[NYP][DM];
__device__ __align__(128) uint32_t g_pre[NRED][32];
__device__ __align__(128) uint4 g_op[NFFN][DM / 4];
__device__ __align__(16) unsigned g_epoch[4] = {1, 0, 0, 0};
__device__ unsigned g_ticket[2];
#define DBG_STAMP(i) do { } while (0)
#define DBG_CLK(v) do { } while (0)

struct Params {
    const __nv_bfloat16* x;
    const __nv_bfloat16* c;
    const unsigned* epoch;
    const __nv_bfloat16* k;
    const __nv_bfloat16* v;
    const __nv_bfloat16* wq;
    const __nv_bfloat16* wo;
    const __nv_bfloat16* wg;
    const __nv_bfloat16* wu;
    const __nv_bfloat16* wd;
    const __nv_bfloat16* wmod;
    __nv_bfloat16* out;
};

constexpr int SM_RING = 0;
constexpr int SM_Q = SM_RING + NSLOT * 2 * TILE_BYTES;
constexpr int SM_FLRED = SM_Q + NH * DH * 2;
constexpr int SM_FLML = SM_FLRED + 2 * 4 * DH * 4;
constexpr int SM_SC = SM_FLML + 64;
constexpr int SM_H = SM_SC + DM * 4;
constexpr int SM_GA = SM_H + DM * 4;
constexpr int SM_CB1 = SM_GA + DM * 4;
constexpr int SM_SB = SM_CB1 + DM * 4;
constexpr int SM_X1 = SM_SB + DM * 4;
constexpr int SM_RED = SM_X1 + DM * 4;
constexpr int SM_ST = SM_RED + 8 * 32 * 4;
constexpr int SM_RR = SM_ST + 64;
constexpr int RR_STRIDE = 36;
constexpr int SM_META = SM_RR + 2 * 4 * RR_STRIDE * 4;
constexpr int SM_BAR = SM_META + 64;
constexpr int NBAR = 4 * NSLOT + 5;
constexpr int SM_TOTAL = SM_BAR + NBAR * 8;
constexpr int SM_WM = SM_Q;
constexpr int SM_WQ = SM_RING + (NSLOT - 1) * 2 * TILE_BYTES;
constexpr int SM_CX = SM_GA;
constexpr int WD_STRIDE = DM * 2 + 16;
static_assert(NFFN > 96 && NFFN <= 128, "final_reduce record mapping");
static_assert(SM_META % 16 == 0 && SM_CX % 16 == 0 && SM_ST % 16 == 0 && SM_BAR % 8 == 0, "smem alignment");

constexpr int BAR_ALL256 = 1, BAR_CONS = 2, BAR_AUX = 3;

__device__ __forceinline__ uint32_t smem_u32(const void* p) { return (uint32_t)__cvta_generic_to_shared(p); }
__device__ __forceinline__ void bar_sync(int id, int n) { asm volatile("bar.sync %0, %1;" ::"r"(id), "r"(n) : "memory"); }

__device__ __forceinline__ bool bar_and(int id, int n, int pred) {
    uint32_t r;
    asm volatile("{\n\t.reg .pred p, q;\n\tsetp.ne.u32 p, %3, 0;\n\tbar.red.and.pred q, %1, %2, p;\n\tselp.u32 %0, 1, 0, q;\n\t}"
                 : "=r"(r) : "r"(id), "r"(n), "r"(pred) : "memory");
    return r != 0;
}
__device__ __forceinline__ void mbar_init(uint32_t bar, uint32_t cnt) {
    asm volatile("mbarrier.init.shared::cta.b64 [%0], %1;" ::"r"(bar), "r"(cnt) : "memory");
}
__device__ __forceinline__ void mbar_expect_tx(uint32_t bar, uint32_t bytes) {
    asm volatile("mbarrier.arrive.expect_tx.shared::cta.b64 _, [%0], %1;" ::"r"(bar), "r"(bytes) : "memory");
}
__device__ __forceinline__ void mbar_arrive(uint32_t bar) {
    asm volatile("mbarrier.arrive.shared::cta.b64 _, [%0];" ::"r"(bar) : "memory");
}
__device__ __forceinline__ bool mbar_try(uint32_t bar, uint32_t parity) {
    uint32_t ok;
    asm volatile("{\n\t.reg .pred p;\n\tmbarrier.try_wait.parity.shared::cta.b64 p, [%1], %2;\n\tselp.u32 %0, 1, 0, p;\n\t}"
                 : "=r"(ok) : "r"(bar), "r"(parity) : "memory");
    return ok != 0;
}
__device__ __noinline__ void mbar_wait_slow(uint32_t bar, uint32_t parity) {
    long long t0 = clock64();
    while (!mbar_try(bar, parity)) {
        if (clock64() - t0 > 4000000000ll) __trap();
    }
}
__device__ __forceinline__ void mbar_wait(uint32_t bar, uint32_t parity) {
    if (mbar_try(bar, parity)) return;
    if (mbar_try(bar, parity)) return;
    mbar_wait_slow(bar, parity);
}
__device__ __forceinline__ void bulk_g2s(uint32_t dst, const void* src, uint32_t bytes, uint32_t bar, uint64_t pol) {
    asm volatile("cp.async.bulk.shared::cluster.global.mbarrier::complete_tx::bytes.L2::cache_hint [%0], [%1], %2, [%3], %4;"
                 ::"r"(dst), "l"(src), "r"(bytes), "r"(bar), "l"(pol) : "memory");
}
__device__ __forceinline__ void tma_2d(uint32_t dst, const CUtensorMap* tm, int x, int y, uint32_t bar) {
    asm volatile("cp.async.bulk.tensor.2d.shared::cluster.global.mbarrier::complete_tx::bytes [%0], [%1, {%3, %4}], [%2];"
                 ::"r"(dst), "l"(tm), "r"(bar), "r"(x), "r"(y) : "memory");
}
__device__ __forceinline__ uint4 ldg_nc16(const void* p) {
    uint4 v;
    asm volatile("ld.global.nc.L1::no_allocate.L2::128B.v4.u32 {%0,%1,%2,%3}, [%4];" : "=r"(v.x), "=r"(v.y), "=r"(v.z), "=r"(v.w) : "l"(p));
    return v;
}
__device__ __forceinline__ uint32_t ldg_nc2(const void* p) {
    uint32_t v;
    asm volatile("ld.global.nc.L1::no_allocate.u16 %0, [%1];" : "=r"(v) : "l"(p));
    return v;
}
__device__ __forceinline__ uint4 ld_ll16(const void* p) {
    uint4 v;
    asm volatile("ld.relaxed.gpu.global.v4.u32 {%0,%1,%2,%3}, [%4];" : "=r"(v.x), "=r"(v.y), "=r"(v.z), "=r"(v.w) : "l"(p) : "memory");
    return v;
}
__device__ __forceinline__ uint2 ld_ll8(const void* p) {
    uint2 v;
    asm volatile("ld.relaxed.gpu.global.v2.u32 {%0,%1}, [%2];" : "=r"(v.x), "=r"(v.y) : "l"(p) : "memory");
    return v;
}
__device__ __forceinline__ uint2 ld_ll8_p(const void* p, uint32_t live) {
    uint2 v = make_uint2(0u, 0u);
    asm volatile("{\n\t.reg .pred q;\n\tsetp.ne.u32 q, %3, 0;\n\t@q ld.relaxed.gpu.global.v2.u32 {%0,%1}, [%2];\n\t}"
                 : "+r"(v.x), "+r"(v.y) : "l"(p), "r"(live) : "memory");
    return v;
}
__device__ __forceinline__ void st_ll8(void* p, uint32_t a, uint32_t tag) {
    asm volatile("st.relaxed.gpu.global.v2.u32 [%0], {%1,%2};" ::"l"(p), "r"(a), "r"(tag) : "memory");
}
__device__ __forceinline__ void st_u32(void* p, uint32_t a) {
    asm volatile("st.relaxed.gpu.global.u32 [%0], %1;" ::"l"(p), "r"(a) : "memory");
}
__device__ __forceinline__ void st_u32x2(void* p, uint32_t a, uint32_t b) {
    asm volatile("st.relaxed.gpu.global.v2.u32 [%0], {%1,%2};" ::"l"(p), "r"(a), "r"(b) : "memory");
}
__device__ __forceinline__ void st_u32x4(void* p, uint32_t a, uint32_t b, uint32_t c, uint32_t d) {
    asm volatile("st.relaxed.gpu.global.v4.u32 [%0], {%1,%2,%3,%4};" ::"l"(p), "r"(a), "r"(b), "r"(c), "r"(d) : "memory");
}
__device__ __forceinline__ void ld16_if(uint4& v, const void* p, uint32_t need) {
    asm volatile("{\n\t.reg .pred q;\n\tsetp.ne.u32 q, %5, 0;\n\t@q ld.relaxed.gpu.global.v4.u32 {%0,%1,%2,%3}, [%4];\n\t}"
                 : "+r"(v.x), "+r"(v.y), "+r"(v.z), "+r"(v.w) : "l"(p), "r"(need) : "memory");
}
__device__ __forceinline__ void ld8_if(uint2& v, const void* p, uint32_t need) {
    asm volatile("{\n\t.reg .pred q;\n\tsetp.ne.u32 q, %3, 0;\n\t@q ld.relaxed.gpu.global.v2.u32 {%0,%1}, [%2];\n\t}"
                 : "+r"(v.x), "+r"(v.y) : "l"(p), "r"(need) : "memory");
}
__device__ __forceinline__ void ld_rec_if(uint4& v, uint2& m, const void* pv, const void* pm, uint32_t need) {
    asm volatile("{\n\t.reg .pred q;\n\tsetp.ne.u32 q, %8, 0;\n\t@q ld.relaxed.gpu.global.v4.u32 {%0,%1,%2,%3}, [%6];\n\t"
                 "@q ld.relaxed.gpu.global.v2.u32 {%4,%5}, [%7];\n\t}"
                 : "+r"(v.x), "+r"(v.y), "+r"(v.z), "+r"(v.w), "+r"(m.x), "+r"(m.y) : "l"(pv), "l"(pm), "r"(need) : "memory");
}
__device__ __forceinline__ uint32_t ld_u32_p(const void* p, uint32_t live) {
    uint32_t v = 0;
    asm volatile("{\n\t.reg .pred q;\n\tsetp.ne.u32 q, %2, 0;\n\t@q ld.relaxed.gpu.global.u32 %0, [%1];\n\t}"
                 : "+r"(v) : "l"(p), "r"(live) : "memory");
    return v;
}
__device__ __forceinline__ uint32_t opaque(uint32_t v) {
    uint32_t r;
    asm volatile("mov.u32 %0, %1;" : "=r"(r) : "r"(v));
    return r;
}
template <typename T> __device__ __forceinline__ T* opaque_ptr(T* v) {
    T* r;
    asm volatile("mov.u64 %0, %1;" : "=l"(r) : "l"(v));
    return r;
}
__device__ __forceinline__ uint32_t tag8_of(unsigned tag) { return tag % 255u + 1u; }
__device__ __forceinline__ uint32_t w_pack(float v, uint32_t t8) { return (__float_as_uint(v) & 0xffffff00u) | t8; }
__device__ __forceinline__ float w_val(uint32_t w) { return __uint_as_float(w & 0xffffff00u); }
__device__ __forceinline__ uint32_t w_bad4(const uint4& v, uint32_t t8) { return ((v.x ^ t8) | (v.y ^ t8) | (v.z ^ t8) | (v.w ^ t8)) & 0xffu; }
__device__ __forceinline__ void spin_cycles(unsigned n) {
    unsigned t0, t;
    asm volatile("mov.u32 %0, %%clock;" : "=r"(t0) :: "memory");
    do { asm volatile("mov.u32 %0, %%clock;" : "=r"(t) :: "memory"); } while (t - t0 < n);
}
struct Spin {
    unsigned n = 0;
    __device__ __forceinline__ void tick() { if (++n > (1u << 22)) __trap(); }
};

__device__ __forceinline__ float bf_lo(uint32_t v) { return __uint_as_float(v << 16); }
__device__ __forceinline__ float bf_hi(uint32_t v) { return __uint_as_float(v & 0xffff0000u); }
__device__ __forceinline__ float bfr(float x) {
    uint32_t r;
    asm("cvt.rn.bf16x2.f32 %0, %1, %2;" : "=r"(r) : "f"(x), "f"(0.f));
    return __uint_as_float(r);
}
__device__ __forceinline__ uint32_t pack_bf2(float lo, float hi) {
    uint32_t r;
    asm("cvt.rn.bf16x2.f32 %0, %1, %2;" : "=r"(r) : "f"(hi), "f"(lo));
    return r;
}
__device__ __forceinline__ float ex2(float x) {
    float r;
    asm("ex2.approx.ftz.f32 %0, %1;" : "=f"(r) : "f"(x));
    return r;
}
__device__ __forceinline__ void fma8(float (&acc)[8], const uint4& w, float s) {
    acc[0] = fmaf(s, bf_lo(w.x), acc[0]); acc[1] = fmaf(s, bf_hi(w.x), acc[1]);
    acc[2] = fmaf(s, bf_lo(w.y), acc[2]); acc[3] = fmaf(s, bf_hi(w.y), acc[3]);
    acc[4] = fmaf(s, bf_lo(w.z), acc[4]); acc[5] = fmaf(s, bf_hi(w.z), acc[5]);
    acc[6] = fmaf(s, bf_lo(w.w), acc[6]); acc[7] = fmaf(s, bf_hi(w.w), acc[7]);
}
__device__ __forceinline__ float treduce8(const float (&v)[8], int lane) {
    const bool b4 = lane & 16, b3 = lane & 8, b2 = lane & 4;
    float w[4], z[2];
#pragma unroll
    for (int i = 0; i < 4; i++) {
        float keep = b4 ? v[i + 4] : v[i], send = b4 ? v[i] : v[i + 4];
        w[i] = keep + __shfl_xor_sync(0xffffffffu, send, 16);
    }
#pragma unroll
    for (int i = 0; i < 2; i++) {
        float keep = b3 ? w[i + 2] : w[i], send = b3 ? w[i] : w[i + 2];
        z[i] = keep + __shfl_xor_sync(0xffffffffu, send, 8);
    }
    float keep = b2 ? z[1] : z[0], send = b2 ? z[0] : z[1];
    return keep + __shfl_xor_sync(0xffffffffu, send, 4);
}
__device__ __forceinline__ int treduce8_index(int lane) { return ((lane >> 4) & 1) * 4 + ((lane >> 3) & 1) * 2 + ((lane >> 2) & 1); }

__device__ __forceinline__ void mma_bf16(float (&c)[4], uint32_t a0, uint32_t a1, uint32_t a2, uint32_t a3, uint32_t b0, uint32_t b1) {
    asm volatile("mma.sync.aligned.m16n8k16.row.col.f32.bf16.bf16.f32 {%0,%1,%2,%3}, {%4,%5,%6,%7}, {%8,%9}, {%0,%1,%2,%3};"
                 : "+f"(c[0]), "+f"(c[1]), "+f"(c[2]), "+f"(c[3])
                 : "r"(a0), "r"(a1), "r"(a2), "r"(a3), "r"(b0), "r"(b1));
}
__device__ __forceinline__ uint4 lds16(uint32_t addr) {
    uint4 v;
    asm volatile("ld.shared.v4.u32 {%0,%1,%2,%3}, [%4];" : "=r"(v.x), "=r"(v.y), "=r"(v.z), "=r"(v.w) : "r"(addr));
    return v;
}
__device__ __forceinline__ uint4 lds16v(uint32_t addr) {
    uint4 v;
    asm volatile("ld.shared.v4.u32 {%0,%1,%2,%3}, [%4];" : "=r"(v.x), "=r"(v.y), "=r"(v.z), "=r"(v.w) : "r"(addr) : "memory");
    return v;
}
__device__ __forceinline__ float lds_f32(uint32_t addr) {
    float v;
    asm volatile("ld.shared.f32 %0, [%1];" : "=f"(v) : "r"(addr) : "memory");
    return v;
}
__device__ __forceinline__ float2 lds_f32x2(uint32_t addr) {
    float2 v;
    asm volatile("ld.shared.v2.f32 {%0,%1}, [%2];" : "=f"(v.x), "=f"(v.y) : "r"(addr) : "memory");
    return v;
}
__device__ __forceinline__ float4 lds_f32x4(uint32_t addr) {
    float4 v;
    asm volatile("ld.shared.v4.f32 {%0,%1,%2,%3}, [%4];" : "=f"(v.x), "=f"(v.y), "=f"(v.z), "=f"(v.w) : "r"(addr) : "memory");
    return v;
}
__device__ __forceinline__ void sts_u32(uint32_t addr, uint32_t v) { asm volatile("st.shared.u32 [%0], %1;" ::"r"(addr), "r"(v) : "memory"); }
__device__ __forceinline__ void sts_f32(uint32_t addr, float v) { asm volatile("st.shared.f32 [%0], %1;" ::"r"(addr), "f"(v) : "memory"); }
__device__ __forceinline__ void sts_f32x2(uint32_t addr, float a, float b) {
    asm volatile("st.shared.v2.f32 [%0], {%1,%2};" ::"r"(addr), "f"(a), "f"(b) : "memory");
}
__device__ __forceinline__ float rcp_ftz(float x) {
    float r;
    asm("rcp.approx.ftz.f32 %0, %1;" : "=f"(r) : "f"(x));
    return r;
}
__device__ __forceinline__ uint4 ldmatrix_x4_trans(uint32_t addr) {
    uint4 v;
    asm volatile("ldmatrix.sync.aligned.m8n8.x4.trans.shared.b16 {%0,%1,%2,%3}, [%4];"
                 : "=r"(v.x), "=r"(v.y), "=r"(v.z), "=r"(v.w) : "r"(addr));
    return v;
}

__device__ __forceinline__ void ln_warp_stats(float v0, float v1, uint32_t dst, bool wr) {
    const float shift = __shfl_sync(0xffffffffu, v0, 0);
    const float d0 = v0 - shift, d1 = v1 - shift;
    float s1 = d0 + d1, s2 = fmaf(d0, d0, d1 * d1);
#pragma unroll
    for (int o = 16; o > 0; o >>= 1) {
        s1 += __shfl_xor_sync(0xffffffffu, s1, o);
        s2 += __shfl_xor_sync(0xffffffffu, s2, o);
    }
    if (wr) sts_f32x2(dst, fmaf(s1, 1.0f / 64, shift), fmaxf(fmaf(-s1 * (1.0f / 64), s1, s2), 0.f));
}
__device__ __forceinline__ void ln_combine(uint32_t st, float& mean_b, float& rden) {
    const float4 a = lds_f32x4(st), b = lds_f32x4(st + 16), c = lds_f32x4(st + 32), d = lds_f32x4(st + 48);
    const float mean = (((a.x + a.z) + (b.x + b.z)) + ((c.x + c.z) + (d.x + d.z))) * 0.125f;
    const float e0 = a.x - mean, e1 = a.z - mean, e2 = b.x - mean, e3 = b.z - mean;
    const float e4 = c.x - mean, e5 = c.z - mean, e6 = d.x - mean, e7 = d.z - mean;
    const float between = (fmaf(e0, e0, e1 * e1) + fmaf(e2, e2, e3 * e3)) + (fmaf(e4, e4, e5 * e5) + fmaf(e6, e6, e7 * e7));
    const float within = ((a.y + a.w) + (b.y + b.w)) + ((c.y + c.w) + (d.y + d.w));
    const float var = fmaf(between, 64.f, within) * (1.0f / DM);
    mean_b = bfr(mean);
    float sq;
    asm("sqrt.approx.ftz.f32 %0, %1;" : "=f"(sq) : "f"(bfr(bfr(var) + 1e-5f)));
    rden = rcp_ftz(bfr(sq));
}
__device__ __forceinline__ float ln_mod(float x, float mean_b, float rden, float scale1, float shift) {
    const float n = bfr(bfr(x - mean_b) * rden);
    return bfr(bfr(n * scale1) + shift);
}

__device__ __forceinline__ uint32_t* op_of(int cta, int tid) {
    const int lane = tid & 31, warp = tid >> 5, g = lane >> 2, t = lane & 3;
    return reinterpret_cast<uint32_t*>(&g_op[cta][warp * 16 + t * 4 + (g >> 1)]) + (g & 1) * 2;
}

__device__ __noinline__ void ffn_tail(const uint32_t sbase, const uint32_t tid, const uint32_t t8, uint32_t* const op,
                                      const uint32_t* const yp, const uint32_t live) {
    const uint32_t lane = tid & 31, warp = tid >> 5;
    const uint32_t g = lane >> 2, t = lane & 3;
    const uint32_t* fp = PRE_MODE == 2 ? &g_pre[lane >> 2][(lane & 3) * 2] : &g_pre[lane & 7][0];
    uint32_t v0 = 0;
    if (live) {
        bar_sync(BAR_ALL256, 256);
        st_u32x2(op, 0u, 0u);
        mbar_wait(sbase + SM_BAR + (4 * NSLOT + 3) * 8, 0);
    }
    if (warp == 0) v0 = ld_u32_p(fp, live);
    if (tid == 0) DBG_STAMP(18);
    uint4 wgu[8], wdn[4];
    {
        const uint32_t r = lane & 7;
        const uint2 ffn = make_uint2(__float_as_uint(lds_f32(sbase + SM_META + 48)), __float_as_uint(lds_f32(sbase + SM_META + 52)));
        const uint32_t wa = sbase + ffn.x + (warp >> 2) * 16384 +
                            ((warp & 3) * 128 + r + (lane >> 4) * 8) * 32 + ((((lane >> 3) ^ (r >> 2)) & 1) * 16);
#pragma unroll
        for (int i = 0; i < 8; i++) wgu[i] = ldmatrix_x4_trans(wa + i * 512);
        const uint32_t wb = sbase + ffn.y + (r + (lane >> 4) * 8) * WD_STRIDE + warp * 128 + ((lane >> 3) & 1) * 16;
#pragma unroll
        for (int j = 0; j < 4; j++) wdn[j] = ldmatrix_x4_trans(wb + j * 32);
    }
    const float2 ga = lds_f32x2(sbase + SM_GA + tid * 8), cb1 = lds_f32x2(sbase + SM_CB1 + tid * 8);
    const float2 sb = lds_f32x2(sbase + SM_SB + tid * 8);
    float2 xo = lds_f32x2(sbase + SM_X1 + tid * 8);
    const uint32_t h_dst = sbase + SM_H + ((tid & ~15u) + (tid & 3) * 4 + ((tid >> 2) & 3)) * 4;
    const uint32_t h_src = sbase + SM_H + (warp & 3) * 256 + t * 16;
    const uint32_t st_dst = sbase + SM_ST + warp * 8;
    const uint32_t red_dst = sbase + SM_RED + (warp * 16 + g) * 4;
    const uint32_t red_src = sbase + SM_RED + ((lane >> 4) * 64 + (lane & 15)) * 4;
    const bool st_wr = lane == 0 && live, red_wr = t == 0 && live;
    Spin sp;
    if (warp == 0 || !live) {
        while (true) {
            const uint32_t v1 = ld_u32_p(fp, live);
            if (PRE_VOTE((v0 & 0xffu) == t8) || !live) break;
            v0 = ld_u32_p(fp, live);
            if (PRE_VOTE((v1 & 0xffu) == t8)) break;
            sp.tick();
        }
    }
    if (tid == 0) DBG_STAMP(13);
    if (live) bar_sync(BAR_ALL256, 256);
    {
        uint2 yv[NYP];
#pragma unroll
        for (int c = 0; c < NYP; c++) yv[c] = make_uint2(0u, 0u);
        static_assert(NYP == 4, "y partials");
        asm volatile("{\n\t.reg .pred q;\n\tsetp.ne.u32 q, %9, 0;\n\t"
                     "@q ld.relaxed.gpu.global.v2.u32 {%0,%1}, [%8];\n\t"
                     "@q ld.relaxed.gpu.global.v2.u32 {%2,%3}, [%8+2048];\n\t"
                     "@q ld.relaxed.gpu.global.v2.u32 {%4,%5}, [%8+4096];\n\t"
                     "@q ld.relaxed.gpu.global.v2.u32 {%6,%7}, [%8+6144];\n\t}"
                     : "+r"(yv[0].x), "+r"(yv[0].y), "+r"(yv[1].x), "+r"(yv[1].y), "+r"(yv[2].x), "+r"(yv[2].y), "+r"(yv[3].x), "+r"(yv[3].y)
                     : "l"(yp), "r"(live) : "memory");
        while (true) {
            uint32_t bad = 0;
#pragma unroll
            for (int c = 0; c < NYP; c++) bad |= ((yv[c].x ^ t8) | (yv[c].y ^ t8)) & 0xffu;
            if (__all_sync(0xffffffffu, bad == 0 || !live)) break;
#pragma unroll
            for (int c = 0; c < NYP; c++) ld8_if(yv[c], yp + c * DM, ((yv[c].x ^ t8) | (yv[c].y ^ t8)) & 0xffu);
            sp.tick();
        }
        const float a0 = (w_val(yv[0].x) + w_val(yv[1].x)) + (w_val(yv[2].x) + w_val(yv[3].x));
        const float a1 = (w_val(yv[0].y) + w_val(yv[1].y)) + (w_val(yv[2].y) + w_val(yv[3].y));
        xo.x = bfr(xo.x + bfr(ga.x * bfr(a0)));
        xo.y = bfr(xo.y + bfr(ga.y * bfr(a1)));
    }
    if (tid == 0) DBG_STAMP(7);
    FIN_GO(1)
    ln_warp_stats(xo.x, xo.y, st_dst, st_wr);
    if (live) bar_sync(BAR_ALL256, 256);
    float mean_b, rden;
    ln_combine(sbase + SM_ST, mean_b, rden);
    const uint32_t hv = pack_bf2(ln_mod(xo.x, mean_b, rden, cb1.x, sb.x), ln_mod(xo.y, mean_b, rden, cb1.y, sb.y));
    if (live) {
        sts_u32(h_dst, hv);
        bar_sync(BAR_ALL256, 256);
    }
    if (tid == 0) DBG_STAMP(15);
    FIN_GO(2)
    {
        uint4 b[4];
#pragma unroll
        for (int i = 0; i < 4; i++) b[i] = lds16v(h_src + i * 64);
        float c[8][4];
#pragma unroll
        for (int i = 0; i < 4; i++) {
#pragma unroll
            for (int e = 0; e < 4; e++) { c[2 * i][e] = 0.f; c[2 * i + 1][e] = 0.f; }
            mma_bf16(c[2 * i], wgu[2 * i].x, wgu[2 * i].y, wgu[2 * i].z, wgu[2 * i].w, b[i].x, b[i].y);
            mma_bf16(c[2 * i + 1], wgu[2 * i + 1].x, wgu[2 * i + 1].y, wgu[2 * i + 1].z, wgu[2 * i + 1].w, b[i].z, b[i].w);
        }
        const float r0 = ((c[0][0] + c[1][0]) + (c[2][0] + c[3][0])) + ((c[4][0] + c[5][0]) + (c[6][0] + c[7][0]));
        const float r1 = ((c[0][2] + c[1][2]) + (c[2][2] + c[3][2])) + ((c[4][2] + c[5][2]) + (c[6][2] + c[7][2]));
        if (red_wr) { sts_f32(red_dst, r0); sts_f32(red_dst + 32, r1); }
    }
    FIN_GO(3)
    if (live) bar_sync(BAR_ALL256, 256);
    if (tid == 0) DBG_STAMP(16);
    FIN_GO(4)
    {
        float s = (lds_f32(red_src) + lds_f32(red_src + 64)) + (lds_f32(red_src + 128) + lds_f32(red_src + 192));
        s = bfr(s);
        const float u = __shfl_down_sync(0xffffffffu, s, 16);
        constexpr float GC1 = -2.0f * LOG2E * 0.7978845608028654f;
        const float ge = bfr(s * rcp_ftz(1.0f + ex2(s * fmaf(s * s, GC1 * 0.044715f, GC1))));
        const float act = bfr(ge * u);
        const uint32_t pk = pack_bf2(act, __shfl_down_sync(0xffffffffu, act, 1));
        const uint32_t b0 = __shfl_sync(0xffffffffu, pk, 2 * t), b1 = __shfl_sync(0xffffffffu, pk, 2 * t + 8);
        float o0 = 0.f, o1 = 0.f;
#pragma unroll
        for (int j = 0; j < 4; j++) {
            float c[4] = {0.f, 0.f, 0.f, 0.f};
            mma_bf16(c, wdn[j].x, wdn[j].y, wdn[j].z, wdn[j].w, b0, b1);
            if (t == (uint32_t)j) { o0 = c[0]; o1 = c[2]; }
        }
        if (live) st_u32x2(op, w_pack(o0, t8), w_pack(o1, t8));
        FIN_GO(5)
        if (tid == 0) DBG_STAMP(8);
    }
}

__device__ __noinline__ void final_reduce(const __nv_bfloat16* x, __nv_bfloat16* out, const int cg, const unsigned tag, const uint32_t live) {
    const int lane = threadIdx.x & 31;
    const uint32_t t8 = tag8_of(tag);
    const int cbase = (cg >> 2) * 16 + (cg & 3) * 2;
    const int col = cbase + ((lane >> 1) & 1) + (lane & 1) * 8;
    float x1c;
    uint2 gav, gbv;
    {
        Spin sp;
        while (true) {
            gav = ld_ll8_p(&g_mod[2 * DM + col], live);
            gbv = ld_ll8_p(&g_mod[5 * DM + col], live);
            if ((gav.y == tag && gbv.y == tag) || !live) break;
            sp.tick();
        }
        const float xin = __uint_as_float(ldg_nc2(x + col) << 16);
        uint32_t yv;
        Spin sp2;
        while (true) {
            yv = ld_u32_p(&g_y[(lane >> 2) & (NYP - 1)][col], live);
            if (__all_sync(0xffffffffu, (yv & 0xffu) == t8 || !live)) break;
            spin_cycles(200);
            sp2.tick();
        }
        float a = w_val(yv);
        a += __shfl_xor_sync(0xffffffffu, a, 4);
        a += __shfl_xor_sync(0xffffffffu, a, 8);
        x1c = bfr(xin + bfr(__uint_as_float(gav.x) * bfr(a)));
    }
    if (FIN_GATE && live) {
        extern __shared__ __align__(1024) unsigned char smem[];
        if (cg < NFFN) {
            Spin sq;
            uint32_t go;
            do { asm volatile("ld.volatile.shared.u32 %0, [%1];" : "=r"(go) : "r"(smem_u32(smem) + SM_META + 60) : "memory"); sq.tick(); } while (go == 0);
        } else {
            spin_cycles(FIN_DELAY);
        }
    }
    uint4 ov[4];
    Spin sp;
    {
        const uint4* src = &g_op[lane][cg];
        uint32_t bad[4];
#pragma unroll
        for (int k = 0; k < 4; k++) { ov[k] = make_uint4(0u, 0u, 0u, 0u); bad[k] = live; }
        if (lane >= NFFN - 96) { ov[3] = make_uint4(t8, t8, t8, t8); bad[3] = 0u; }
        while (true) {
            asm volatile("{\n\t.reg .pred q0, q1, q2, q3;\n\t"
                         "setp.ne.u32 q0, %17, 0;\n\tsetp.ne.u32 q1, %18, 0;\n\tsetp.ne.u32 q2, %19, 0;\n\tsetp.ne.u32 q3, %20, 0;\n\t"
                         "@q0 ld.relaxed.gpu.global.v4.u32 {%0,%1,%2,%3}, [%16];\n\t"
                         "@q1 ld.relaxed.gpu.global.v4.u32 {%4,%5,%6,%7}, [%16+65536];\n\t"
                         "@q2 ld.relaxed.gpu.global.v4.u32 {%8,%9,%10,%11}, [%16+131072];\n\t"
                         "@q3 ld.relaxed.gpu.global.v4.u32 {%12,%13,%14,%15}, [%16+196608];\n\t}"
                         : "+r"(ov[0].x), "+r"(ov[0].y), "+r"(ov[0].z), "+r"(ov[0].w), "+r"(ov[1].x), "+r"(ov[1].y), "+r"(ov[1].z), "+r"(ov[1].w),
                           "+r"(ov[2].x), "+r"(ov[2].y), "+r"(ov[2].z), "+r"(ov[2].w), "+r"(ov[3].x), "+r"(ov[3].y), "+r"(ov[3].z), "+r"(ov[3].w)
                         : "l"(src), "r"(bad[0]), "r"(bad[1]), "r"(bad[2]), "r"(bad[3]) : "memory");
            static_assert(sizeof(g_op[0]) * 32 == 65536, "record stride");
#pragma unroll
            for (int k = 0; k < 4; k++) bad[k] = w_bad4(ov[k], t8);
            if (__all_sync(0xffffffffu, (bad[0] | bad[1] | bad[2] | bad[3]) == 0 || !live)) break;
            sp.tick();
        }
    }
    float f;
    {
        const float a0 = (w_val(ov[0].x) + w_val(ov[1].x)) + (w_val(ov[2].x) + w_val(ov[3].x));
        const float a1 = (w_val(ov[0].y) + w_val(ov[1].y)) + (w_val(ov[2].y) + w_val(ov[3].y));
        const float a2 = (w_val(ov[0].z) + w_val(ov[1].z)) + (w_val(ov[2].z) + w_val(ov[3].z));
        const float a3 = (w_val(ov[0].w) + w_val(ov[1].w)) + (w_val(ov[2].w) + w_val(ov[3].w));
        const bool b1 = lane & 2, b0 = lane & 1;
        const float z0 = (b1 ? a2 : a0) + __shfl_xor_sync(0xffffffffu, b1 ? a0 : a2, 2);
        const float z1 = (b1 ? a3 : a1) + __shfl_xor_sync(0xffffffffu, b1 ? a1 : a3, 2);
        f = (b0 ? z1 : z0) + __shfl_xor_sync(0xffffffffu, b0 ? z0 : z1, 1);
        f += __shfl_xor_sync(0xffffffffu, f, 4);
        f += __shfl_xor_sync(0xffffffffu, f, 8);
        f += __shfl_xor_sync(0xffffffffu, f, 16);
        f = bfr(f);
    }
    const float res = bfr(x1c + bfr(__uint_as_float(gbv.x) * f));
    if (lane < 4 && live) *reinterpret_cast<unsigned short*>(out + col) = (unsigned short)(__float_as_uint(res) >> 16);
    if (cg == 0 && lane == 0 && live) *reinterpret_cast<volatile unsigned*>(&g_epoch[0]) = (tag + 1u) ? (tag + 1u) : 1u;
    if (lane == 0) DBG_STAMP(9);
}

__global__ void __launch_bounds__(NTHREADS, 1)
adaLN_cond__mha_block_cached__geglu_ffn__decode_kernel(const Params p, const __grid_constant__ CUtensorMap tm_mod,
                                                       const __grid_constant__ CUtensorMap tm_q,
                                                       const __grid_constant__ CUtensorMap tm_g,
                                                       const __grid_constant__ CUtensorMap tm_u) {
    DBG_CLK(ck0);
    extern __shared__ __align__(1024) unsigned char smem[];
    const int tid = threadIdx.x;
    const int lane = tid & 31;
    const int warp = tid >> 5;
    const int cta = blockIdx.x;
    const int G = gridDim.x;
    const uint32_t sbase = smem_u32(smem);
    const uint32_t bar_fullK = sbase + SM_BAR, bar_fullV = bar_fullK + NSLOT * 8;
    const uint32_t bar_emptyK = bar_fullV + NSLOT * 8, bar_emptyV = bar_emptyK + NSLOT * 8;
    const uint32_t bar_wm = bar_emptyV + NSLOT * 8, bar_wq = bar_wm + 8, bar_wqfree = bar_wm + 16, bar_ffn = bar_wm + 24;
    const uint32_t bar_cx = bar_wm + 32;
    volatile uint32_t* s_meta = reinterpret_cast<volatile uint32_t*>(smem + SM_META);

    volatile uint32_t* s_tag = reinterpret_cast<volatile uint32_t*>(smem + SM_META + 32);
    volatile uint32_t* s_ffn = reinterpret_cast<volatile uint32_t*>(smem + SM_META + 48);
    const uint32_t s_qready = sbase + SM_META + 56;

    uint64_t pol;
    asm volatile("createpolicy.fractional.L2::evict_first.b64 %0, 1.0;" : "=l"(pol));
    const char* kp = reinterpret_cast<const char*>(p.k);
    const char* vp = reinterpret_cast<const char*>(p.v);
    if (tid == 8 * 32) {
        const int cs = cta < NSLICE ? cta : NSLICE - 1;
        auto issue_k0 = [&]() {
            mbar_expect_tx(bar_fullK, TILE_BYTES);
            bulk_g2s(sbase + SM_RING, kp + (size_t)cta * TILE_BYTES, TILE_BYTES, bar_fullK, pol);
        };
        auto issue_v0 = [&]() {
            mbar_expect_tx(bar_fullV, TILE_BYTES);
            bulk_g2s(sbase + SM_RING + TILE_BYTES, vp + (size_t)cta * TILE_BYTES, TILE_BYTES, bar_fullV, pol);
        };
        auto issue_small = [&]() {
            uint64_t pol_n;
            asm volatile("createpolicy.fractional.L2::evict_normal.b64 %0, 1.0;" : "=l"(pol_n));
            mbar_expect_tx(bar_cx, 2 * DM * 2 + 16);
            bulk_g2s(sbase + SM_CX, p.c, DM * 2, bar_cx, pol_n);
            bulk_g2s(sbase + SM_CX + DM * 2, p.x, DM * 2, bar_cx, pol_n);
            bulk_g2s(sbase + SM_META + 32, p.epoch, 16, bar_cx, pol_n);
            mbar_expect_tx(bar_wm, 128 * 32 * 2);
            tma_2d(sbase + SM_WM, &tm_mod, (cs >> 2) * 32, (cs & 3) * 128, bar_wm);
        };
        auto issue_k1 = [&]() {
            mbar_expect_tx(bar_fullK + 8, TILE_BYTES);
            bulk_g2s(sbase + SM_RING + 2 * TILE_BYTES, kp + (size_t)(cta + G) * TILE_BYTES, TILE_BYTES, bar_fullK + 8, pol);
        };
        mbar_init(bar_fullK, 1);
        mbar_init(bar_fullV, 1);
        if (PRO_K1) mbar_init(bar_fullK + 8, 1);
        mbar_init(bar_cx, 1);
        mbar_init(bar_wm, 1);
        mbar_init(bar_wq, 1);
        asm volatile("fence.mbarrier_init.release.cluster;" ::: "memory");
        auto issue_wq = [&]() {
            mbar_expect_tx(bar_wq, 128 * 128 * 2);
            tma_2d(sbase + SM_WQ, &tm_q, (cs >> 2) * 128, (cs & 3) * 128, bar_wq);
        };
        if (PRO_ORDER == 0) { issue_small(); issue_k0(); issue_v0(); issue_wq(); }
        else if (PRO_ORDER == 1) { issue_k0(); issue_small(); issue_v0(); issue_wq(); }
        else if (PRO_ORDER == 2) { issue_k0(); issue_v0(); issue_small(); issue_wq(); }
        else if (PRO_ORDER == 3) { issue_k0(); issue_v0(); issue_k1(); issue_small(); issue_wq(); }
        else if (PRO_ORDER == 4) { issue_k0(); issue_v0(); issue_small(); issue_k1(); issue_wq(); }
        else if (PRO_ORDER == 5) { issue_k0(); issue_small(); issue_wq(); issue_v0(); }
        else { issue_small(); issue_wq(); issue_k0(); issue_v0(); }
#pragma unroll
        for (int i = 0; i < NSLOT; i++) {
            if (i > 0) { if (!(PRO_K1 && i == 1)) mbar_init(bar_fullK + i * 8, 1); mbar_init(bar_fullV + i * 8, 1); }
            mbar_init(bar_emptyK + i * 8, 4);
            mbar_init(bar_emptyV + i * 8, 4);
        }
        mbar_init(bar_wqfree, 1);
        mbar_init(bar_ffn, 1);
        s_meta[0] = 0;
        s_meta[1] = 0;
        s_ffn[0] = 0; s_ffn[1] = 0;
        asm volatile("st.shared.v2.u32 [%0], {%1, %1};" ::"r"(s_qready), "r"(0) : "memory");
        asm volatile("fence.mbarrier_init.release.cluster;" ::: "memory");
    }

    if (warp == 8) {
        __syncwarp();
        asm volatile("bar.arrive 0, %0;" ::"r"(NTHREADS) : "memory");
        unsigned tag = 0;
        if (lane == 0) {
            const unsigned dyn0 = NSLOT * G;
            unsigned nn = cta + G - dyn0;
            int slot = 1;
            uint32_t ph = 1;
            int wslot = 0, wkv = 0;
            uint32_t wph = 0;
            int inflight = PRO_K1 ? 3 : 2;
            int win = WIN_PRE;
            auto window = [&]() {
                if (inflight >= win) {
                    mbar_wait((wkv ? bar_fullV : bar_fullK) + wslot * 8, wph);
                    if (wkv) { wkv = 0; if (++wslot == NSLOT) { wslot = 0; wph ^= 1; } } else wkv = 1;
                } else {
                    inflight++;
                }
            };
            auto next_unit = [&](int i) {
                if (i + 1 < NSLOT) nn = cta + (i + 1) * G - dyn0;
                else asm volatile("atom.relaxed.gpu.global.add.u32 %0, [%1], 1;" : "=r"(nn) : "l"(&g_ticket[tag & 1]) : "memory");
            };
            for (int i = 1; ; i++) {
                const unsigned tk = nn + dyn0;
                if (tk >= NT) break;
                const bool half = tk >= NU1;
                const unsigned cur = half ? NU1 + ((tk - NU1) >> 1) : tk;
                const uint32_t bytes = half ? TILE_BYTES / 2 : TILE_BYTES;
                const size_t goff = (size_t)cur * TILE_BYTES + (half ? ((tk - NU1) & 1) * (TILE_BYTES / 2) : 0);
                if (half) win = 2 * WIN_TILES;
                if (win < WIN_TILES) {
                    uint32_t qr;
                    asm volatile("ld.volatile.shared.u32 %0, [%1];" : "=r"(qr) : "r"(s_qready) : "memory");
                    if (qr != 0 || i >= NSLOT) win = WIN_TILES;
                }
                if (i == NSLOT - 2) { mbar_wait(bar_cx, 0); tag = *s_tag; }
                const uint32_t dst = sbase + SM_RING + slot * (2 * TILE_BYTES);
                if (i == NSLOT - 1) mbar_wait(bar_wqfree, 0);
                if (!(PRO_K1 && i == 1)) {
                    mbar_wait(bar_emptyK + slot * 8, ph);
                    window();
                    s_meta[slot] = cur / UNITS_PER_HEAD | (half ? 0x100u : 0u);
                    mbar_expect_tx(bar_fullK + slot * 8, bytes);
                    bulk_g2s(dst, kp + goff, bytes, bar_fullK + slot * 8, pol);
                }
                if (TICKET_EARLY) next_unit(i);
                mbar_wait(bar_emptyV + slot * 8, ph);
                window();
                mbar_expect_tx(bar_fullV + slot * 8, bytes);
                bulk_g2s(dst + TILE_BYTES, vp + goff, bytes, bar_fullV + slot * 8, pol);
                if (!TICKET_EARLY) next_unit(i);
                if (++slot == NSLOT) { slot = 0; ph ^= 1; }
            }
            mbar_wait(bar_emptyK + slot * 8, ph);
            s_meta[slot] = NH;
            mbar_arrive(bar_fullK + slot * 8);
            DBG_STAMP(1);
            if (cta == 0) g_ticket[(tag + 1) & 1] = 0;
            if (cta < NFFN) {
                asm volatile("prefetch.tensormap [%0];" ::"l"(&tm_g) : "memory");
                asm volatile("prefetch.tensormap [%0];" ::"l"(&tm_u) : "memory");
                const uint32_t d0 = SM_RING + slot * (2 * TILE_BYTES);
                mbar_wait(bar_emptyK + slot * 8, ph);
                mbar_wait(bar_emptyV + slot * 8, ph);
                if (++slot == NSLOT) { slot = 0; ph ^= 1; }
                const uint32_t d1 = SM_RING + slot * (2 * TILE_BYTES);
                mbar_wait(bar_emptyK + slot * 8, ph);
                mbar_wait(bar_emptyV + slot * 8, ph);
                s_ffn[0] = d0; s_ffn[1] = d1;
                while (inflight > FFN_KEEP) {
                    mbar_wait((wkv ? bar_fullV : bar_fullK) + wslot * 8, wph);
                    if (wkv) { wkv = 0; if (++wslot == NSLOT) { wslot = 0; wph ^= 1; } } else wkv = 1;
                    inflight--;
                }
                mbar_expect_tx(bar_ffn, 3 * TILE_BYTES);
                tma_2d(sbase + d0, &tm_g, cta * 16, 0, bar_ffn);
                tma_2d(sbase + d0 + 8192, &tm_g, cta * 16, 256, bar_ffn);
                tma_2d(sbase + d0 + 16384, &tm_u, cta * 16, 0, bar_ffn);
                tma_2d(sbase + d0 + 24576, &tm_u, cta * 16, 256, bar_ffn);
#pragma unroll 1
                for (int r = 0; r < 16; r++)
                    bulk_g2s(sbase + d1 + r * WD_STRIDE, reinterpret_cast<const char*>(p.wd) + (size_t)(cta * 16 + r) * (DM * 2),
                             DM * 2, bar_ffn, pol);
                DBG_STAMP(17);
            }
        }
        __syncwarp();
        if (cta < NFIN) {
            mbar_wait(bar_cx, 0);
            tag = *s_tag;
            final_reduce(p.x, p.out, cta, tag, 1u);
        }
        return;
    }

    float* s_sc = reinterpret_cast<float*>(smem + SM_SC);
    float* s_h = reinterpret_cast<float*>(smem + SM_H);
    float* s_red = reinterpret_cast<float*>(smem + SM_RED);
    float* s_x1 = reinterpret_cast<float*>(smem + SM_X1);
    unsigned tag;
    {
        const bool has_slice = cta < NSLICE;
        const int cs = has_slice ? cta : NSLICE - 1;
        const int rq = cs & 3;
        if (has_slice) {
            if (warp == 7) st_ll8(&g_mp[rq][(cs >> 2) * 32 + lane], 0u, 0u);
            if (tid < DH) st_ll8(&g_qp[cs >> 2][rq][tid], 0u, 0u);
        }
        if (tid < DH) {
            st_u32(&g_po[0][cta][tid], 0u);
            st_u32(&g_po[1][cta][tid], 0u);
            if (tid < 8) { st_u32(&g_pml[0][cta][tid], 0u); st_u32(&g_pml[1][cta][tid], 0u); }
        }
        bar_sync(0, NTHREADS);
        mbar_wait(bar_cx, 0);
        tag = *s_tag;
        if (tid == 0) DBG_STAMP(10);
        {
            const unsigned short* sc16 = reinterpret_cast<const unsigned short*>(smem + SM_CX);
            const float cf0 = __uint_as_float((uint32_t)sc16[tid] << 16), cf1 = __uint_as_float((uint32_t)sc16[tid + 256] << 16);
            const uint32_t xme = *reinterpret_cast<const uint32_t*>(smem + SM_CX + DM * 2 + tid * 4);
            const float2 xm = make_float2(bf_lo(xme), bf_hi(xme));
            ln_warp_stats(xm.x, xm.y, sbase + SM_ST + warp * 8, lane == 0);
            s_sc[tid] = bfr(__fdiv_rn(cf0, 1.0f + expf(-cf0)));
            s_sc[tid + 256] = bfr(__fdiv_rn(cf1, 1.0f + expf(-cf1)));
            *reinterpret_cast<float2*>(s_x1 + 2 * tid) = xm;
        }
        bar_sync(BAR_ALL256, 256);
        mbar_wait(bar_wm, 0);
        if (tid == 0) DBG_STAMP(12);
        {
            float acc[8] = {0.f, 0.f, 0.f, 0.f, 0.f, 0.f, 0.f, 0.f};
            const uint4 w0 = lds16(sbase + SM_WM + tid * 16), w1 = lds16(sbase + SM_WM + 4096 + tid * 16);
            fma8(acc, w0, s_sc[rq * 128 + (tid >> 2)]);
            fma8(acc, w1, s_sc[rq * 128 + 64 + (tid >> 2)]);
            const float r = treduce8(acc, lane);
            s_red[warp * 32 + (lane & 3) * 8 + treduce8_index(lane)] = r;
        }
        bar_sync(BAR_ALL256, 256);
        if (warp == 7) {
            const float* rp = s_red + lane;
            const float s = ((rp[0] + rp[32]) + (rp[64] + rp[96])) + ((rp[128] + rp[160]) + (rp[192] + rp[224]));
            if (has_slice) st_ll8(&g_mp[rq][(cs >> 2) * 32 + lane], __float_as_uint(s), tag);
            if (lane == 0) DBG_STAMP(2);
        } else if (warp < 4) {
            float mean_b, rden;
            ln_combine(sbase + SM_ST, mean_b, rden);
            const int col = rq * 128 + tid;
            const float xn = bfr(bfr(s_x1[col] - mean_b) * rden);
            uint2 a[4], b[4];
            Spin sp;
#pragma unroll
            for (int k = 0; k < 4; k++) { a[k] = make_uint2(0u, 0u); b[k] = make_uint2(0u, 0u); }
            while (true) {
                uint32_t bad = 0;
#pragma unroll
                for (int k = 0; k < 4; k++) { ld8_if(a[k], &g_mp[k][col], a[k].y ^ tag); ld8_if(b[k], &g_mp[k][DM + col], b[k].y ^ tag); }
#pragma unroll
                for (int k = 0; k < 4; k++) bad |= (a[k].y ^ tag) | (b[k].y ^ tag);
                if (bad == 0) break;
                if (PRE_SPIN) spin_cycles(PRE_SPIN);
                sp.tick();
            }
            const float sa = bfr((__uint_as_float(a[0].x) + __uint_as_float(a[1].x)) + (__uint_as_float(a[2].x) + __uint_as_float(a[3].x)));
            const float ca = bfr((__uint_as_float(b[0].x) + __uint_as_float(b[1].x)) + (__uint_as_float(b[2].x) + __uint_as_float(b[3].x)));
            s_h[tid] = bfr(bfr(xn * bfr(1.0f + ca)) + sa);
            if (tid == 0) DBG_STAMP(11);
        }
        mbar_wait(bar_wq, 0);
        bar_sync(BAR_ALL256, 256);
        if (tid == 0) DBG_STAMP(3);
        {
            float acc[8] = {0.f, 0.f, 0.f, 0.f, 0.f, 0.f, 0.f, 0.f};
            const uint32_t wa = sbase + SM_WQ + tid * 16;
#pragma unroll
            for (int i = 0; i < 8; i++) fma8(acc, lds16(wa + i * 4096), s_h[(tid >> 4) + 16 * i]);
            const bool hi = lane & 16;
            float4 r;
            r.x = (hi ? acc[4] : acc[0]) + __shfl_xor_sync(0xffffffffu, hi ? acc[0] : acc[4], 16);
            r.y = (hi ? acc[5] : acc[1]) + __shfl_xor_sync(0xffffffffu, hi ? acc[1] : acc[5], 16);
            r.z = (hi ? acc[6] : acc[2]) + __shfl_xor_sync(0xffffffffu, hi ? acc[2] : acc[6], 16);
            r.w = (hi ? acc[7] : acc[3]) + __shfl_xor_sync(0xffffffffu, hi ? acc[3] : acc[7], 16);
            *reinterpret_cast<float4*>(smem + SM_FLRED + warp * 512 + (lane & 15) * 32 + (lane >> 4) * 16) = r;
        }
        bar_sync(BAR_ALL256, 256);
        if (tid == 128) mbar_arrive(bar_wqfree);
        if (tid < DH) {
            const float* rp = reinterpret_cast<const float*>(smem + SM_FLRED) + tid;
            const float s = ((rp[0] + rp[128]) + (rp[256] + rp[384])) + ((rp[512] + rp[640]) + (rp[768] + rp[896]));
            if (has_slice) st_ll8(&g_qp[cs >> 2][rq][tid], __float_as_uint(s), tag);
            if (tid == 0) DBG_STAMP(14);
            bar_sync(BAR_CONS, 128);
        }
    }

    if (warp < 4) {
        const int g = lane >> 2, t = lane & 3;
        const uint32_t kofs0 = warp * 4096 + g * 256 + t * 16 + 64 * (g & 1);
        const uint32_t kofs1 = warp * 4096 + g * 256 + t * 16 + 64 * ((g & 1) ^ 1);
        const uint32_t qofs0 = t * 16 + 64 * (g & 1), qofs1 = t * 16 + 64 * ((g & 1) ^ 1);
        uint32_t vofs[8];
        {
            const uint32_t vrow = (lane & 7) + 8 * (lane >> 4);
            const uint32_t vch = (((lane >> 3) & 1) + (lane & 7)) * 16;
#pragma unroll
            for (int mt = 0; mt < 8; mt++) vofs[mt] = TILE_BYTES + warp * 4096 + vrow * 256 + ((vch + 32 * mt) & 255);
        }
        const bool diag = (t == (g >> 1));
        const uint32_t sel0 = diag ? ((g & 1) ? 0x1044u : 0x4410u) : 0x4444u;
        const uint32_t sel1 = diag ? ((g & 1) ? 0x3244u : 0x4432u) : 0x4444u;

        float acc[8][4];
#pragma unroll
        for (int i = 0; i < 8; i++) { acc[i][0] = acc[i][1] = acc[i][2] = acc[i][3] = 0.f; }
        float m_run = -INFINITY, l_run = 0.f;
        uint4 qf[4];
        const uint32_t t8 = tag8_of(tag);
        uint32_t fl_dst[4];
#pragma unroll
        for (int k = 0; k < 4; k++)
            fl_dst[k] = opaque(sbase + SM_FLRED + (warp * DH + ((4 * k + 2 * (t >> 1) + (t & 1) + 2 * t) & 15) * 8 + g) * 4);
        uint32_t* const po_dst = opaque_ptr(&g_po[0][cta][tid]);
        uint32_t* const pml_dst = opaque_ptr(&g_pml[0][cta][tid & 7]);
        int cur_head = -1;
        int nflush = 0;
        int slot = 0;
        uint32_t ph = 0;
        while (true) {
            const uint32_t base = sbase + SM_RING + slot * (2 * TILE_BYTES);
            mbar_wait(bar_fullK + slot * 8, ph);
            const uint32_t meta = s_meta[slot];
            const int head = meta & 0xff;
            if (head != cur_head) {
                if (cur_head >= 0) {
                float sum[16];
#pragma unroll
                for (int mt = 0; mt < 8; mt++) {
                    sum[2 * mt] = acc[mt][0] + acc[(mt + 7) & 7][3];
                    sum[2 * mt + 1] = acc[mt][1] + acc[mt][2];
                }
                float r[8], f4[4];
#pragma unroll
                for (int j = 0; j < 8; j++) {
                    const float keep = (t & 1) ? sum[2 * j + 1] : sum[2 * j];
                    const float send = (t & 1) ? sum[(2 * j + 14) & 15] : sum[(2 * j + 3) & 15];
                    r[j] = keep + __shfl_xor_sync(0xffffffffu, send, 1);
                }
#pragma unroll
                for (int k = 0; k < 4; k++) {
                    const float keep = (t & 2) ? r[2 * k + 1] : r[2 * k];
                    const float send = (t & 2) ? r[(2 * k + 6) & 7] : r[(2 * k + 3) & 7];
                    f4[k] = keep + __shfl_xor_sync(0xffffffffu, send, 2);
                }
                float lw = l_run;
                lw += __shfl_xor_sync(0xffffffffu, lw, 4);
                lw += __shfl_xor_sync(0xffffffffu, lw, 8);
                lw += __shfl_xor_sync(0xffffffffu, lw, 16);
                const uint32_t fpar = (nflush & 1) * (4 * DH * 4);
                const uint32_t fml = sbase + SM_FLML + (nflush & 1) * 32;
#pragma unroll
                for (int k = 0; k < 4; k++) sts_f32(fl_dst[k] + fpar, f4[k]);
                if (lane == 0) sts_f32x2(fml + warp * 8, m_run, lw);
                bar_sync(BAR_CONS, 128);
                {
                    const float4 s01 = lds_f32x4(fml), s23 = lds_f32x4(fml + 16);
                    const uint32_t fr = sbase + SM_FLRED + fpar + tid * 4;
                    const float o0 = lds_f32(fr), o1 = lds_f32(fr + DH * 4), o2 = lds_f32(fr + 2 * DH * 4), o3 = lds_f32(fr + 3 * DH * 4);
                    const float M = fmaxf(fmaxf(s01.x, s01.z), fmaxf(s23.x, s23.z));
                    const float e0 = ex2((s01.x - M) * LOG2E), e1 = ex2((s01.z - M) * LOG2E);
                    const float e2 = ex2((s23.x - M) * LOG2E), e3 = ex2((s23.z - M) * LOG2E);
                    const float o = (e0 * o0 + e1 * o1) + (e2 * o2 + e3 * o3);
                    st_u32(po_dst + cur_head * (MAXG * DH), w_pack(o, t8));
                    if (tid < 8) {
                        const float L = (e0 * s01.y + e1 * s01.w) + (e2 * s23.y + e3 * s23.w);
                        st_u32(pml_dst + cur_head * (MAXG * 32), w_pack(tid == 0 ? M : L, t8));
                    }
                    if (cur_head + 2 < NH) {
                        st_u32(po_dst + (cur_head + 2) * (MAXG * DH), 0u);
                        if (tid < 8) st_u32(pml_dst + (cur_head + 2) * (MAXG * 32), 0u);
                    }
                }
                for (int hh = cur_head + 1; hh < head; hh++) {
                    st_u32(&g_po[hh][cta][tid], t8);
                    if (tid < 8) st_u32(&g_pml[hh][cta][tid], w_pack(tid == 0 ? -INFINITY : 0.f, t8));
                }
                nflush++;
#pragma unroll
                for (int i = 0; i < 8; i++) { acc[i][0] = acc[i][1] = acc[i][2] = acc[i][3] = 0.f; }
                m_run = -INFINITY; l_run = 0.f;
                }
                if (head >= NH) break;
                cur_head = head;
                {
                    uint32_t qr;
                    Spin sp;
                    while (true) {
                        asm volatile("ld.acquire.cta.shared.u32 %0, [%1];" : "=r"(qr) : "r"(s_qready) : "memory");
                        if (qr > (uint32_t)head) break;
                        sp.tick();
                    }
                    if (tid == 0 && head == 0) DBG_STAMP(4);
                }
                const uint32_t qb = sbase + SM_Q + head * 256;
                qf[0] = lds16(qb + qofs0); qf[1] = lds16(qb + qofs1);
                qf[2] = lds16(qb + qofs0 + 128); qf[3] = lds16(qb + qofs1 + 128);
            }
            if ((meta >> 8) && warp >= 2) {
                __syncwarp();
                if (lane == 0) mbar_arrive(bar_emptyK + slot * 8);
                mbar_wait(bar_fullV + slot * 8, ph);
                if (lane == 0) mbar_arrive(bar_emptyV + slot * 8);
                if (++slot == NSLOT) { slot = 0; ph ^= 1; }
                continue;
            }
            uint4 kl[4], kh[4];
            kl[0] = lds16(base + kofs0);        kh[0] = lds16(base + kofs0 + 2048);
            kl[1] = lds16(base + kofs1);        kh[1] = lds16(base + kofs1 + 2048);
            kl[2] = lds16(base + kofs0 + 128);  kh[2] = lds16(base + kofs0 + 2048 + 128);
            kl[3] = lds16(base + kofs1 + 128);  kh[3] = lds16(base + kofs1 + 2048 + 128);
            float ca[4] = {0.f, 0.f, 0.f, 0.f}, cb[4] = {0.f, 0.f, 0.f, 0.f};
#pragma unroll
            for (int i = 0; i < 4; i++) {
                mma_bf16(ca, kl[i].x, kh[i].x, kl[i].y, kh[i].y, qf[i].x, qf[i].y);
                mma_bf16(cb, kl[i].z, kh[i].z, kl[i].w, kh[i].w, qf[i].z, qf[i].w);
            }
            __syncwarp();
            if (lane == 0) mbar_arrive(bar_emptyK + slot * 8);
            const float r_lo = (g & 1) ? (ca[1] + cb[1]) : (ca[0] + cb[0]);
            const float r_hi = (g & 1) ? (ca[3] + cb[3]) : (ca[2] + cb[2]);
            uint32_t pk = pack_bf2(r_lo, r_hi);
            pk = pack_bf2(bf_lo(pk) * QK_SCALE, bf_hi(pk) * QK_SCALE);
            const float s_lo = bf_lo(pk), s_hi = bf_hi(pk);
            const float mx = fmaxf(s_lo, s_hi);
            if (__any_sync(0xffffffffu, mx > m_run)) {
                float wm = mx;
                wm = fmaxf(wm, __shfl_xor_sync(0xffffffffu, wm, 4));
                wm = fmaxf(wm, __shfl_xor_sync(0xffffffffu, wm, 8));
                wm = fmaxf(wm, __shfl_xor_sync(0xffffffffu, wm, 16));
                const float m_new = fmaxf(m_run, wm);
                const float f = ex2((m_run - m_new) * LOG2E);
#pragma unroll
                for (int i = 0; i < 8; i++) { acc[i][0] *= f; acc[i][1] *= f; acc[i][2] *= f; acc[i][3] *= f; }
                l_run *= f;
                m_run = m_new;
            }
            const float p_lo = ex2((s_lo - m_run) * LOG2E), p_hi = ex2((s_hi - m_run) * LOG2E);
            l_run += p_lo + p_hi;
            const uint32_t pp = pack_bf2(p_lo, p_hi);
            const uint32_t b0 = __byte_perm(pp, 0, sel0), b1 = __byte_perm(pp, 0, sel1);

            mbar_wait(bar_fullV + slot * 8, ph);
            uint4 vf[8];
#pragma unroll
            for (int mt = 0; mt < 8; mt++) vf[mt] = ldmatrix_x4_trans(base + vofs[mt]);
#pragma unroll
            for (int mt = 0; mt < 8; mt++) mma_bf16(acc[mt], vf[mt].x, vf[mt].y, vf[mt].z, vf[mt].w, b0, b1);
            __syncwarp();
            if (lane == 0) mbar_arrive(bar_emptyV + slot * 8);

            if (++slot == NSLOT) { slot = 0; ph ^= 1; }
        }
        if (tid == 0) DBG_STAMP(5);
    } else {
        const int at = tid - 128;
        const int awarp = warp - 4;
        auto gather_q = [&](int h) {
            uint2 a[4];
            Spin sp;
#pragma unroll
            for (int k = 0; k < 4; k++) a[k] = make_uint2(0u, 0u);
            while (true) {
                uint32_t bad = 0;
#pragma unroll
                for (int k = 0; k < 4; k++) ld8_if(a[k], &g_qp[h][k][at], a[k].y ^ tag);
#pragma unroll
                for (int k = 0; k < 4; k++) bad |= a[k].y ^ tag;
                if (bad == 0) break;
                if (PRE_SPIN) spin_cycles(PRE_SPIN);
                sp.tick();
            }
            const float q = (__uint_as_float(a[0].x) + __uint_as_float(a[1].x)) + (__uint_as_float(a[2].x) + __uint_as_float(a[3].x));
            *reinterpret_cast<unsigned short*>(smem + SM_Q + h * 256 + at * 2) = (unsigned short)(__float_as_uint(bfr(q)) >> 16);
            bar_sync(BAR_AUX, 128);
            if (at == 0) asm volatile("st.release.cta.shared.u32 [%0], %1;" ::"r"(s_qready), "r"(h + 1) : "memory");
        };
        gather_q(0);
        gather_q(1);
        if (DRY_RUN && cta < NFFN) ffn_tail(opaque(sbase), opaque(tid), tag8_of(tag), op_of(cta, tid), &g_y[0][2 * tid], 0u);
        if (DRY_RUN && warp == 7 && cta < NFIN) final_reduce(p.x, p.out, cta, tag, 0u);
        if (cta < NSLICE) {
            uint4 w[8];
#pragma unroll
            for (int i = 0; i < 8; i++)
                w[i] = ldg_nc16(p.wmod + (size_t)((at >> 1) + 64 * i) * (6 * DM) + 2 * DM + cta * 16 + (at & 1) * 8);
            float acc[8] = {0.f, 0.f, 0.f, 0.f, 0.f, 0.f, 0.f, 0.f};
#pragma unroll
            for (int i = 0; i < 8; i++) fma8(acc, w[i], s_sc[(at >> 1) + 64 * i]);
            float r = treduce8(acc, lane);
            r += __shfl_xor_sync(0xffffffffu, r, 2);
            if ((lane & 2) == 0) s_red[awarp * 32 + (lane & 1) * 8 + treduce8_index(lane)] = r;
            bar_sync(BAR_AUX, 128);
            if (at < 16) {
                const float s = s_red[at] + s_red[32 + at] + s_red[64 + at] + s_red[96 + at];
                st_ll8(&g_mod[2 * DM + cta * 16 + at], __float_as_uint(bfr(s)), tag);
            }
        }
#pragma unroll 1
        for (int h = 2; h < NH; h++) gather_q(h);
        if (cta < NFFN) {
            float* s_ga = reinterpret_cast<float*>(smem + SM_GA);
            float* s_cb1 = reinterpret_cast<float*>(smem + SM_CB1);
            float* s_sb = reinterpret_cast<float*>(smem + SM_SB);
            uint4 v[6];
            Spin sp;
            while (true) {
                uint32_t bad = 0;
#pragma unroll
                for (int i = 0; i < 6; i++) v[i] = ld_ll16(&g_mod[2 * DM + 2 * (at + 128 * i)]);
#pragma unroll
                for (int i = 0; i < 6; i++) bad |= (v[i].y ^ tag) | (v[i].w ^ tag);
                if (bad == 0) break;
                __nanosleep(200);
                sp.tick();
            }
#pragma unroll
            for (int i = 0; i < 2; i++) {
                const int e = 2 * (at + 128 * i);
                s_ga[e] = __uint_as_float(v[i].x); s_ga[e + 1] = __uint_as_float(v[i].z);
                s_sb[e] = __uint_as_float(v[2 + i].x); s_sb[e + 1] = __uint_as_float(v[2 + i].z);
                s_cb1[e] = bfr(1.0f + __uint_as_float(v[4 + i].x)); s_cb1[e + 1] = bfr(1.0f + __uint_as_float(v[4 + i].z));
            }
        } else if (cta < RED0 + NRED) {
            const int c = cta - RED0;
            const int da = c >> 1, cb = c & 1;
            constexpr int NK = MAXG / 16;
            const int j = at & 7, grp = at >> 3;
            const int g = lane >> 2, t = lane & 3;
            const uint32_t t8 = tag8_of(tag);
            float yc[4][4];
#pragma unroll
            for (int i = 0; i < 4; i++) { yc[i][0] = yc[i][1] = yc[i][2] = yc[i][3] = 0.f; }
            const int ilast = min(grp + 16 * (NK - 1), G - 1);
            auto prefetch_wo = [&](int h) {
                if (at == 0 && h < NH)
                    asm volatile("cp.async.bulk.prefetch.L2.global [%0], %1;" ::"l"(p.wo + (size_t)(h * DH + c * 16) * DM), "r"(16 * DM * 2) : "memory");
            };
            uint32_t* const y_dst = opaque_ptr(&g_y[da][cb * 256 + awarp * 64 + g * 8 + 2 * t]);
            uint32_t* const pre_dst = opaque_ptr(PRE_MODE == 2 ? &g_pre[c][awarp * 2] : &g_pre[c][at & 7]);
            prefetch_wo(0);
            prefetch_wo(1);
            for (int h = 0; h < NH; h++) {
                prefetch_wo(h + 2);
                uint32_t wa[8][4];
                {
                    const __nv_bfloat16* wsrc = p.wo + (size_t)(h * DH + da * 32 + 2 * t) * DM + cb * 256 + awarp * 64 + g * 8;
                    uint4 w[2][4];
#pragma unroll
                    for (int ks = 0; ks < 2; ks++) {
                        w[ks][0] = ldg_nc16(wsrc + ks * 16 * DM);              w[ks][1] = ldg_nc16(wsrc + (ks * 16 + 1) * DM);
                        w[ks][2] = ldg_nc16(wsrc + (ks * 16 + 8) * DM);        w[ks][3] = ldg_nc16(wsrc + (ks * 16 + 9) * DM);
                    }
#pragma unroll
                    for (int ks = 0; ks < 2; ks++) {
                        const uint32_t r0[4] = {w[ks][0].x, w[ks][0].y, w[ks][0].z, w[ks][0].w};
                        const uint32_t r1[4] = {w[ks][1].x, w[ks][1].y, w[ks][1].z, w[ks][1].w};
                        const uint32_t r2[4] = {w[ks][2].x, w[ks][2].y, w[ks][2].z, w[ks][2].w};
                        const uint32_t r3[4] = {w[ks][3].x, w[ks][3].y, w[ks][3].z, w[ks][3].w};
#pragma unroll
                        for (int jj = 0; jj < 4; jj++) {
                            wa[4 * ks + jj][0] = __byte_perm(r0[jj], r1[jj], 0x5410);
                            wa[4 * ks + jj][1] = __byte_perm(r0[jj], r1[jj], 0x7632);
                            wa[4 * ks + jj][2] = __byte_perm(r2[jj], r3[jj], 0x5410);
                            wa[4 * ks + jj][3] = __byte_perm(r2[jj], r3[jj], 0x7632);
                        }
                    }
                }
                uint2 ml[NK];
                uint4 ov[NK];
                Spin sp;
                if (h == NH - 1) {
                    st_u32x2(&g_y[da][cb * 256 + at * 2], 0u, 0u);
                    if (at < 8) st_u32(&g_pre[c][at], 0u);
                } else {
                    const int i0 = at, i1 = (at + 128 < G) ? at + 128 : at;
                    while (true) {
                        const uint2 a = ld_ll8(&g_pml[h][i0][0]), b = ld_ll8(&g_pml[h][i1][0]);
                        const int ok = (((a.x ^ t8) | (a.y ^ t8) | (b.x ^ t8) | (b.y ^ t8)) & 0xffu) == 0;
                        if (bar_and(BAR_AUX, 128, ok)) break;
                        __nanosleep(400);
                        sp.tick();
                    }
                }
                if (h == NH - 1 && at == 0) DBG_STAMP(19);
                {
                    uint32_t bad[NK];
#pragma unroll
                    for (int k = 0; k < NK; k++) { ml[k] = make_uint2(0u, 0u); ov[k] = make_uint4(0u, 0u, 0u, 0u); bad[k] = 1u; }
                    const uint32_t* mlp = &g_pml[h][grp][0];
                    const uint32_t* ovp = &g_po[h][grp][da * 32 + 4 * j];
                    const uint32_t* mll = &g_pml[h][ilast][0];
                    const uint32_t* ovl = &g_po[h][ilast][da * 32 + 4 * j];
                    while (true) {
#pragma unroll
                        for (int k = 0; k < NK - 1; k++) ld_rec_if(ov[k], ml[k], ovp + k * 16 * DH, mlp + k * 16 * 32, bad[k]);
                        ld_rec_if(ov[NK - 1], ml[NK - 1], ovl, mll, bad[NK - 1]);
                        uint32_t any = 0;
#pragma unroll
                        for (int k = 0; k < NK; k++) {
                            bad[k] = (w_bad4(ov[k], t8) | (ml[k].x ^ t8) | (ml[k].y ^ t8)) & 0xffu;
                            any |= bad[k];
                        }
                        if (__all_sync(0xffffffffu, any == 0)) break;
                        sp.tick();
                    }
                }
                if (h == NH - 1 && at == 0) DBG_STAMP(20);
                if (PRE_MODE == 1 && h == NH - 1 && at < 8) st_u32(pre_dst, t8);
                if (PRE_MODE == 2 && h == NH - 1 && lane == 0) st_u32x2(pre_dst, t8, t8);
                if (grp + 16 * (NK - 1) >= G) ml[NK - 1].x = __float_as_uint(-INFINITY);
                static_assert(NK == 9, "max tree");
                float M = fmaxf(fmaxf(fmaxf(w_val(ml[0].x), w_val(ml[1].x)), fmaxf(w_val(ml[2].x), w_val(ml[3].x))),
                                fmaxf(fmaxf(w_val(ml[4].x), w_val(ml[5].x)), fmaxf(w_val(ml[6].x), w_val(ml[7].x))));
                M = fmaxf(M, w_val(ml[8].x));
                M = fmaxf(M, __shfl_xor_sync(0xffffffffu, M, 8));
                M = fmaxf(M, __shfl_xor_sync(0xffffffffu, M, 16));
                const float Ms = (M == -INFINITY) ? 0.f : M;
                float a0 = 0.f, a1 = 0.f, a2 = 0.f, a3 = 0.f, L = 0.f;
#pragma unroll
                for (int k = 0; k < NK; k++) {
                    const float w = ex2((w_val(ml[k].x) - Ms) * LOG2E);
                    a0 = fmaf(w, w_val(ov[k].x), a0);
                    a1 = fmaf(w, w_val(ov[k].y), a1);
                    a2 = fmaf(w, w_val(ov[k].z), a2);
                    a3 = fmaf(w, w_val(ov[k].w), a3);
                    L = fmaf(w, w_val(ml[k].y), L);
                }
                {
                    const bool b4 = lane & 16, b3 = lane & 8;
                    const float z0 = (b4 ? a2 : a0) + __shfl_xor_sync(0xffffffffu, b4 ? a0 : a2, 16);
                    const float z1 = (b4 ? a3 : a1) + __shfl_xor_sync(0xffffffffu, b4 ? a1 : a3, 16);
                    L += __shfl_xor_sync(0xffffffffu, L, 16);
                    a0 = (b3 ? z1 : z0) + __shfl_xor_sync(0xffffffffu, b3 ? z0 : z1, 8);
                    L += __shfl_xor_sync(0xffffffffu, L, 8);
                }
                float* rr = reinterpret_cast<float*>(smem + SM_RR) + (h & 1) * (4 * RR_STRIDE);
                rr[awarp * RR_STRIDE + 4 * j + ((lane >> 4) & 1) * 2 + ((lane >> 3) & 1)] = a0;
                if (lane == 0) { rr[awarp * RR_STRIDE + 32] = M; rr[awarp * RR_STRIDE + 33] = L; }
                bar_sync(BAR_AUX, 128);
                if (PRE_MODE == 0 && h == NH - 1 && at < 8) st_u32(pre_dst, t8);
                {
                    float2 st[4], v[4][4];
#pragma unroll
                    for (int w = 0; w < 4; w++) {
                        st[w] = *reinterpret_cast<const float2*>(rr + w * RR_STRIDE + 32);
#pragma unroll
                        for (int q = 0; q < 4; q++) v[w][q] = *reinterpret_cast<const float2*>(rr + w * RR_STRIDE + 2 * t + 8 * q);
                    }
                    const float MM = fmaxf(fmaxf(st[0].x, st[1].x), fmaxf(st[2].x, st[3].x));
                    const float e0 = ex2((st[0].x - MM) * LOG2E), e1 = ex2((st[1].x - MM) * LOG2E);
                    const float e2 = ex2((st[2].x - MM) * LOG2E), e3 = ex2((st[3].x - MM) * LOG2E);
                    const float rl = rcp_ftz((e0 * st[0].y + e1 * st[1].y) + (e2 * st[2].y + e3 * st[3].y));
                    uint32_t bq[4];
#pragma unroll
                    for (int q = 0; q < 4; q++)
                        bq[q] = pack_bf2((e0 * v[0][q].x + e1 * v[1][q].x + e2 * v[2][q].x + e3 * v[3][q].x) * rl,
                                         (e0 * v[0][q].y + e1 * v[1][q].y + e2 * v[2][q].y + e3 * v[3][q].y) * rl);
#pragma unroll
                    for (int jj = 0; jj < 4; jj++) mma_bf16(yc[jj], wa[jj][0], wa[jj][1], wa[jj][2], wa[jj][3], bq[0], bq[1]);
#pragma unroll
                    for (int jj = 0; jj < 4; jj++) mma_bf16(yc[jj], wa[4 + jj][0], wa[4 + jj][1], wa[4 + jj][2], wa[4 + jj][3], bq[2], bq[3]);
                }
            }
            {
                float v0 = yc[0][0], v1 = yc[0][2];
#pragma unroll
                for (int jj = 1; jj < 4; jj++) if (t == jj) { v0 = yc[jj][0]; v1 = yc[jj][2]; }
                st_u32x2(y_dst, w_pack(v0, t8), w_pack(v1, t8));
            }
            if (at == 0) DBG_STAMP(6);
        }
    }

    if (cta < NFFN) ffn_tail(opaque(sbase), opaque(tid), tag8_of(tag), op_of(cta, tid), &g_y[0][2 * tid], 1u);
}

}

extern "C" void kernel_launch(void* const* d_in, const int* in_sizes, int n_in, void* d_out, int out_size) {
    (void)in_sizes; (void)n_in; (void)out_size;
    typedef CUresult (*EncodeFn)(CUtensorMap*, CUtensorMapDataType, cuuint32_t, void*, const cuuint64_t*, const cuuint64_t*,
                                 const cuuint32_t*, const cuuint32_t*, CUtensorMapInterleave, CUtensorMapSwizzle,
                                 CUtensorMapL2promotion, CUtensorMapFloatOOBfill);
    static int num_sms = 0;
    static EncodeFn encode = nullptr;
    static void* epoch_ptr = nullptr;
    if (num_sms == 0) {
        int dev = 0;
        cudaGetDevice(&dev);
        cudaDeviceGetAttribute(&num_sms, cudaDevAttrMultiProcessorCount, dev);
        cudaFuncSetAttribute(adaLN_cond__mha_block_cached__geglu_ffn__decode_kernel,
                             cudaFuncAttributeMaxDynamicSharedMemorySize, SM_TOTAL);
        void* fn = nullptr;
        cudaDriverEntryPointQueryResult qr;
        cudaGetDriverEntryPoint("cuTensorMapEncodeTiled", &fn, cudaEnableDefault, &qr);
        encode = (EncodeFn)fn;
        cudaGetSymbolAddress(&epoch_ptr, g_epoch);
    }
#define PROMO_F CU_TENSOR_MAP_L2_PROMOTION_NONE
#define PROMO_M CU_TENSOR_MAP_L2_PROMOTION_NONE
    auto make_map = [&](void* base, int cols, int box_cols, int box_rows, CUtensorMapL2promotion promo, CUtensorMapSwizzle swz) {
        CUtensorMap tm;
        const cuuint64_t gdim[2] = {(cuuint64_t)cols, (cuuint64_t)DM};
        const cuuint64_t gstride[1] = {(cuuint64_t)cols * 2};
        const cuuint32_t box[2] = {(cuuint32_t)box_cols, (cuuint32_t)box_rows};
        const cuuint32_t estr[2] = {1u, 1u};
        encode(&tm, CU_TENSOR_MAP_DATA_TYPE_BFLOAT16, 2, base, gdim, gstride, box, estr, CU_TENSOR_MAP_INTERLEAVE_NONE,
               swz, promo, CU_TENSOR_MAP_FLOAT_OOB_FILL_NONE);
        return tm;
    };
    const CUtensorMap tm_mod = make_map(d_in[10], 6 * DM, 32, 128, PROMO_M, CU_TENSOR_MAP_SWIZZLE_NONE);
    const CUtensorMap tm_q = make_map(d_in[3], NH * DH, 128, 128, PROMO_M, CU_TENSOR_MAP_SWIZZLE_NONE);
    const CUtensorMap tm_g = make_map(d_in[6], FF, 16, 256, PROMO_F, CU_TENSOR_MAP_SWIZZLE_32B);
    const CUtensorMap tm_u = make_map(d_in[7], FF, 16, 256, PROMO_F, CU_TENSOR_MAP_SWIZZLE_32B);
    Params p;
    p.x = (const __nv_bfloat16*)d_in[0];
    p.k = (const __nv_bfloat16*)d_in[1];
    p.v = (const __nv_bfloat16*)d_in[2];
    p.wq = (const __nv_bfloat16*)d_in[3];
    p.wo = (const __nv_bfloat16*)d_in[4];
    p.wg = (const __nv_bfloat16*)d_in[6];
    p.wu = (const __nv_bfloat16*)d_in[7];
    p.wd = (const __nv_bfloat16*)d_in[8];
    p.c = (const __nv_bfloat16*)d_in[9];
    p.epoch = (const unsigned*)epoch_ptr;
    p.wmod = (const __nv_bfloat16*)d_in[10];
    p.out = (__nv_bfloat16*)d_out;
    int grid = num_sms < MAXG ? num_sms : MAXG;
    adaLN_cond__mha_block_cached__geglu_ffn__decode_kernel<<<grid, NTHREADS, SM_TOTAL>>>(p, tm_mod, tm_q, tm_g, tm_u);
}
```
